```python
import torch

def _softmax(x, axis=-1):
    return torch.softmax(x, dim=axis)
def _gelu(x):
    return torch.nn.functional.gelu(x, approximate="tanh")
def _silu(x):
    return torch.nn.functional.silu(x)
def _sigmoid(x):
    return torch.sigmoid(x)
def _layernorm(x, axis=-1, eps=1e-5):
    m = x.mean(dim=axis, keepdim=True)
    v = x.var(dim=axis, keepdim=True, unbiased=False)
    return (x - m) / torch.sqrt(v + eps)
def _scatter_add(tgt, idx, src, axis=0):
    return tgt.clone().index_add_(axis, idx, src)
def _segment_sum(src, seg, n):
    out = torch.zeros((n,) + src.shape[1:], dtype=src.dtype)
    return out.index_add_(0, seg, src)
def _pad(x, pw):
    flat = tuple(v for pair in reversed(pw) for v in pair)
    return torch.nn.functional.pad(x, flat)

kernel_name = 'standalone__gqa_softmax__near_ridge'

def setup_inputs():

    _w = (lambda a: (lambda t: t.to(torch.bfloat16) if t.is_floating_point() else t)(torch.as_tensor(a)))
    B, Hq, Hkv, Sq, Sk, D = 16, 32, 16, 496, 512, 128
    return {
        "q": _w((lambda *s: torch.randn(*s, dtype=torch.bfloat16) * 0.8)(B, Hq, Sq, D)),
        "k": _w((lambda *s: torch.randn(*s, dtype=torch.bfloat16) * 0.8)(B, Hkv, Sk, D)),
        "v": _w((lambda *s: torch.randn(*s, dtype=torch.bfloat16) * 0.05)(B, Hkv, Sk, D)),
    }

def reference(q, k, v):
    B, Hq, Sq, D = q.shape
    Hkv = k.shape[1]
    rep = Hq // Hkv
    k = (lambda x, n, axis: torch.repeat_interleave(x, n, dim=axis))(k, rep, axis=1)
    v = (lambda x, n, axis: torch.repeat_interleave(x, n, dim=axis))(v, rep, axis=1)
    scale = D ** -0.5
    scores = torch.einsum("bhqd,bhkd->bhqk", q, k) * scale
    p = _softmax(scores, axis=-1)
    return torch.einsum("bhqk,bhkd->bhqd", p, v)
```

```cpp
#include <cuda_runtime.h>
#include <cuda_bf16.h>
#include <cuda.h>
#include <stdint.h>
#define DEBUG_TIMEOUT 1

namespace {

constexpr int HD = 128;
constexpr int QROWS = 992;
constexpr int SK = 512;
constexpr int NBH = 256;
constexpr int BN = 128;
constexpr int NBLK = SK / BN;
constexpr int ITEMS_PER_BH = 4;
constexpr int NITEMS = NBH * ITEMS_PER_BH;

constexpr int TILE_BYTES = 128 * 128 * 2;
constexpr int SM_Q = 0;
constexpr int SM_K = 2 * TILE_BYTES;
constexpr int SM_V = 4 * TILE_BYTES;
constexpr int SM_O = 6 * TILE_BYTES;
constexpr int SM_BAR = 7 * TILE_BYTES;
constexpr int SMEM_BYTES = SM_BAR + 256 + 1024;

constexpr int NTHREADS = 384;

enum { B_QF = 0, B_QE = 2, B_KF = 4, B_KE = 6, B_VF = 8, B_VE = 10, B_NUM = 12 };

__device__ __forceinline__ uint32_t smem_u32(const void* p) {
    return (uint32_t)__cvta_generic_to_shared(p);
}
__device__ __forceinline__ void mbar_init(uint32_t bar, uint32_t count) {
    asm volatile("mbarrier.init.shared::cta.b64 [%0], %1;" ::"r"(bar), "r"(count) : "memory");
}
__device__ __forceinline__ void mbar_expect_tx(uint32_t bar, uint32_t bytes) {
    asm volatile("mbarrier.arrive.expect_tx.shared::cta.b64 _, [%0], %1;" ::"r"(bar), "r"(bytes) : "memory");
}
__device__ __forceinline__ void mbar_wait(uint32_t bar, uint32_t parity) {
    uint32_t ok;
    uint32_t it = 0;
    do {
        asm volatile(
            "{\n"
            ".reg .pred p;\n"
            "mbarrier.try_wait.parity.shared::cta.b64 p, [%1], %2;\n"
            "selp.u32 %0, 1, 0, p;\n"
            "}\n"
            : "=r"(ok)
            : "r"(bar), "r"(parity)
            : "memory");
        if (++it > (1u << 22)) __trap();
    } while (!ok);
}
__device__ __forceinline__ void mbar_arrive_cluster(uint32_t bar, uint32_t cta) {
    asm volatile(
        "{\n"
        ".reg .b32 ra;\n"
        "mapa.shared::cluster.u32 ra, %0, %1;\n"
        "mbarrier.arrive.release.cluster.shared::cluster.b64 _, [ra];\n"
        "}\n" ::"r"(bar),
        "r"(cta)
        : "memory");
}
__device__ __forceinline__ void mbar_arrive_local(uint32_t bar) {
    asm volatile("mbarrier.arrive.shared::cta.b64 _, [%0];" ::"r"(bar) : "memory");
}
__device__ __forceinline__ void tma_load_3d(uint32_t dst, const CUtensorMap* tm, uint32_t bar, int c0, int c1,
                                            int c2) {
    asm volatile(
        "cp.async.bulk.tensor.3d.shared::cluster.global.mbarrier::complete_tx::bytes [%0], [%1, {%3, %4, %5}], "
        "[%2];" ::"r"(dst),
        "l"(tm), "r"(bar), "r"(c0), "r"(c1), "r"(c2)
        : "memory");
}
__device__ __forceinline__ void tma_load_3d_mc(uint32_t dst, const CUtensorMap* tm, uint32_t bar, int c0, int c1,
                                               int c2, uint16_t mask) {
    asm volatile(
        "cp.async.bulk.tensor.3d.shared::cluster.global.mbarrier::complete_tx::bytes.multicast::cluster [%0], "
        "[%1, {%3, %4, %5}], [%2], %6;" ::"r"(dst),
        "l"(tm), "r"(bar), "r"(c0), "r"(c1), "r"(c2), "h"(mask)
        : "memory");
}
__device__ __forceinline__ void tma_store_3d(const CUtensorMap* tm, uint32_t src, int c0, int c1, int c2) {
    asm volatile("cp.async.bulk.tensor.3d.global.shared::cta.bulk_group [%0, {%2, %3, %4}], [%1];" ::"l"(tm),
                 "r"(src), "r"(c0), "r"(c1), "r"(c2)
                 : "memory");
}
__device__ __forceinline__ void bar_sync(int id, int n) { asm volatile("bar.sync %0, %1;" ::"r"(id), "r"(n) : "memory"); }
__device__ __forceinline__ void bar_arrive(int id, int n) {
    asm volatile("bar.arrive %0, %1;" ::"r"(id), "r"(n) : "memory");
}
__device__ __forceinline__ void wgmma_fence() { asm volatile("wgmma.fence.sync.aligned;" ::: "memory"); }
__device__ __forceinline__ void wgmma_commit() { asm volatile("wgmma.commit_group.sync.aligned;" ::: "memory"); }
template <int N>
__device__ __forceinline__ void wgmma_wait() {
    asm volatile("wgmma.wait_group.sync.aligned %0;" ::"n"(N) : "memory");
}
__device__ __forceinline__ void fence_regs(float (&d)[64]) {
#pragma unroll
    for (int i = 0; i < 64; i++) asm volatile("" : "+f"(d[i])::"memory");
}
__device__ __forceinline__ void fence_regs_u(uint32_t (&d)[32]) {
#pragma unroll
    for (int i = 0; i < 32; i++) asm volatile("" : "+r"(d[i])::"memory");
}

__device__ __forceinline__ uint64_t make_desc(uint32_t addr, uint32_t lbo_bytes, uint32_t sbo_bytes) {
    uint64_t d = 0;
    d |= (uint64_t)((addr & 0x3FFFF) >> 4);
    d |= (uint64_t)(lbo_bytes >> 4) << 16;
    d |= (uint64_t)(sbo_bytes >> 4) << 32;
    d |= (uint64_t)1 << 62;
    return d;
}

#define ACC64(d)                                                                                                       \
    "+f"(d[0]), "+f"(d[1]), "+f"(d[2]), "+f"(d[3]), "+f"(d[4]), "+f"(d[5]), "+f"(d[6]), "+f"(d[7]), "+f"(d[8]),        \
        "+f"(d[9]), "+f"(d[10]), "+f"(d[11]), "+f"(d[12]), "+f"(d[13]), "+f"(d[14]), "+f"(d[15]), "+f"(d[16]),         \
        "+f"(d[17]), "+f"(d[18]), "+f"(d[19]), "+f"(d[20]), "+f"(d[21]), "+f"(d[22]), "+f"(d[23]), "+f"(d[24]),        \
        "+f"(d[25]), "+f"(d[26]), "+f"(d[27]), "+f"(d[28]), "+f"(d[29]), "+f"(d[30]), "+f"(d[31]), "+f"(d[32]),        \
        "+f"(d[33]), "+f"(d[34]), "+f"(d[35]), "+f"(d[36]), "+f"(d[37]), "+f"(d[38]), "+f"(d[39]), "+f"(d[40]),        \
        "+f"(d[41]), "+f"(d[42]), "+f"(d[43]), "+f"(d[44]), "+f"(d[45]), "+f"(d[46]), "+f"(d[47]), "+f"(d[48]),        \
        "+f"(d[49]), "+f"(d[50]), "+f"(d[51]), "+f"(d[52]), "+f"(d[53]), "+f"(d[54]), "+f"(d[55]), "+f"(d[56]),        \
        "+f"(d[57]), "+f"(d[58]), "+f"(d[59]), "+f"(d[60]), "+f"(d[61]), "+f"(d[62]), "+f"(d[63])

#define ACC64_STR                                                                                                      \
    "{%0, %1, %2, %3, %4, %5, %6, %7, %8, %9, %10, %11, %12, %13, %14, %15, %16, %17, %18, %19, %20, %21, %22, %23, "  \
    "%24, %25, %26, %27, %28, %29, %30, %31, %32, %33, %34, %35, %36, %37, %38, %39, %40, %41, %42, %43, %44, %45, "   \
    "%46, %47, %48, %49, %50, %51, %52, %53, %54, %55, %56, %57, %58, %59, %60, %61, %62, %63}"

template <int SCALE_D>
__device__ __forceinline__ void wgmma_ss(float (&d)[64], uint64_t da, uint64_t db) {
    asm volatile(
        "{\n"
        "wgmma.mma_async.sync.aligned.m64n128k16.f32.bf16.bf16 " ACC64_STR
        ", %64, %65, %66, 1, 1, 0, 0;\n"
        "}\n"
        : ACC64(d)
        : "l"(da), "l"(db), "n"(SCALE_D));
}
__device__ __forceinline__ void wgmma_rs(float (&d)[64], uint32_t a0, uint32_t a1, uint32_t a2, uint32_t a3,
                                         uint64_t db, int scale_d) {
    asm volatile(
        "{\n"
        ".reg .pred p;\n"
        "setp.ne.b32 p, %69, 0;\n"
        "wgmma.mma_async.sync.aligned.m64n128k16.f32.bf16.bf16 " ACC64_STR
        ", {%64, %65, %66, %67}, %68, p, 1, 1, 1;\n"
        "}\n"
        : ACC64(d)
        : "r"(a0), "r"(a1), "r"(a2), "r"(a3), "l"(db), "r"(scale_d));
}

__device__ __forceinline__ float ex2(float x) {
    float y;
    asm("ex2.approx.ftz.f32 %0, %1;" : "=f"(y) : "f"(x));
    return y;
}
__device__ __forceinline__ uint32_t pack_bf16(float lo, float hi) {
    uint32_t r;
    asm("cvt.rn.bf16x2.f32 %0, %1, %2;" : "=r"(r) : "f"(hi), "f"(lo));
    return r;
}

__device__ __forceinline__ void issue_qk(float (&s)[64], uint32_t q_addr, uint32_t k_addr) {
    uint64_t da = make_desc(q_addr, 16, 1024);
    uint64_t db = make_desc(k_addr, 16, 1024);
#pragma unroll
    for (int kk = 0; kk < 8; kk++) {
        uint64_t off = (uint64_t)(((kk >> 2) * 16384 + (kk & 3) * 32) >> 4);
        if (kk == 0)
            wgmma_ss<0>(s, da + off, db + off);
        else
            wgmma_ss<1>(s, da + off, db + off);
    }
}
__device__ __forceinline__ void issue_pv(float (&o)[64], uint32_t (&p)[32], uint32_t v_addr, int accumulate) {
    uint64_t db = make_desc(v_addr, 16384, 1024);
#pragma unroll
    for (int kk = 0; kk < 8; kk++) {
        wgmma_rs(o, p[4 * kk], p[4 * kk + 1], p[4 * kk + 2], p[4 * kk + 3], db + (uint64_t)((kk * 2048) >> 4),
                 kk == 0 ? accumulate : 1);
    }
}

__device__ __forceinline__ void row_max(const float (&s)[64], float& mx0, float& mx1) {
    float a0 = fmaxf(s[0], s[1]), a1 = fmaxf(s[2], s[3]);
    float b0 = fmaxf(s[4], s[5]), b1 = fmaxf(s[6], s[7]);
#pragma unroll
    for (int i = 2; i < 16; i += 2) {
        a0 = fmaxf(a0, fmaxf(s[4 * i], s[4 * i + 1]));
        a1 = fmaxf(a1, fmaxf(s[4 * i + 2], s[4 * i + 3]));
        b0 = fmaxf(b0, fmaxf(s[4 * i + 4], s[4 * i + 5]));
        b1 = fmaxf(b1, fmaxf(s[4 * i + 6], s[4 * i + 7]));
    }
    mx0 = fmaxf(a0, b0);
    mx1 = fmaxf(a1, b1);
    mx0 = fmaxf(mx0, __shfl_xor_sync(0xffffffffu, mx0, 1));
    mx1 = fmaxf(mx1, __shfl_xor_sync(0xffffffffu, mx1, 1));
    mx0 = fmaxf(mx0, __shfl_xor_sync(0xffffffffu, mx0, 2));
    mx1 = fmaxf(mx1, __shfl_xor_sync(0xffffffffu, mx1, 2));
}
__device__ __forceinline__ void row_exp(float (&s)[64], float m0c, float m1c, float c, float& sum0, float& sum1) {
    float x0 = 0.f, x1 = 0.f, y0 = 0.f, y1 = 0.f;
#pragma unroll
    for (int i = 0; i < 16; i++) {
        s[4 * i] = ex2(fmaf(s[4 * i], c, -m0c));
        s[4 * i + 1] = ex2(fmaf(s[4 * i + 1], c, -m0c));
        s[4 * i + 2] = ex2(fmaf(s[4 * i + 2], c, -m1c));
        s[4 * i + 3] = ex2(fmaf(s[4 * i + 3], c, -m1c));
        x0 += s[4 * i];
        y0 += s[4 * i + 1];
        x1 += s[4 * i + 2];
        y1 += s[4 * i + 3];
    }
    sum0 = x0 + y0;
    sum1 = x1 + y1;
}
__device__ __forceinline__ void pack_p(const float (&s)[64], uint32_t (&p)[32]) {
#pragma unroll
    for (int i = 0; i < 32; i++) p[i] = pack_bf16(s[2 * i], s[2 * i + 1]);
}

__global__ void __cluster_dims__(2, 1, 1) __launch_bounds__(NTHREADS, 1)
    gqa_attn_kernel(const __grid_constant__ CUtensorMap tmQ, const __grid_constant__ CUtensorMap tmK,
                    const __grid_constant__ CUtensorMap tmV, const __grid_constant__ CUtensorMap tmO) {
    extern __shared__ uint8_t smem_raw[];
    const uint32_t sbase = (smem_u32(smem_raw) + 1023u) & ~1023u;
    const uint32_t bars = sbase + SM_BAR;
    const int tid = threadIdx.x;
    const int wg = tid >> 7;
    const uint32_t cta_rank = blockIdx.x & 1;
    const int cluster_id = blockIdx.x >> 1;
    const int n_clusters = gridDim.x >> 1;
    const int my_items = (NITEMS - cluster_id + n_clusters - 1) / n_clusters;

    if (tid == 0) {
        for (int s = 0; s < 2; s++) {
            mbar_init(bars + 8 * (B_QF + s), 1);
            mbar_init(bars + 8 * (B_QE + s), 8);
            mbar_init(bars + 8 * (B_KF + s), 1);
            mbar_init(bars + 8 * (B_KE + s), 16);
            mbar_init(bars + 8 * (B_VF + s), 1);
            mbar_init(bars + 8 * (B_VE + s), 16);
        }
        asm volatile("fence.mbarrier_init.release.cluster;" ::: "memory");
    }
    __syncthreads();
    asm volatile("barrier.cluster.arrive.release.aligned;\nbarrier.cluster.wait.acquire.aligned;" ::: "memory");

    if (wg == 0) {
        asm volatile("setmaxnreg.dec.sync.aligned.u32 24;");
        if (tid == 0) {
            asm volatile("prefetch.tensormap [%0];" ::"l"(&tmQ) : "memory");
            asm volatile("prefetch.tensormap [%0];" ::"l"(&tmK) : "memory");
            asm volatile("prefetch.tensormap [%0];" ::"l"(&tmV) : "memory");
            uint32_t kv_cnt = 0;
            for (int it = 0; it < my_items; it++) {
                const int item = cluster_id + it * n_clusters;
                const int bh = item >> 2;
                const int row0 = (item & 3) * 256 + (int)cta_rank * 128;
                {
                    const int qs = it & 1;
                    mbar_wait(bars + 8 * (B_QE + qs), ((it >> 1) & 1) ^ 1);
                    const uint32_t fb = bars + 8 * (B_QF + qs);
                    mbar_expect_tx(fb, TILE_BYTES);
                    const uint32_t dst = sbase + SM_Q + qs * TILE_BYTES;
                    tma_load_3d(dst, &tmQ, fb, 0, row0, bh);
                    tma_load_3d(dst + 16384, &tmQ, fb, 64, row0, bh);
                }
                for (int n = 0; n < NBLK; n++) {
                    const uint32_t s = kv_cnt & 1, ph = ((kv_cnt >> 1) & 1) ^ 1;
                    const int kvrow = n * BN + (int)cta_rank * 64;
                    mbar_wait(bars + 8 * (B_KE + s), ph);
                    {
                        const uint32_t fb = bars + 8 * (B_KF + s);
                        mbar_expect_tx(fb, TILE_BYTES);
                        const uint32_t dst = sbase + SM_K + s * TILE_BYTES + cta_rank * 8192;
                        tma_load_3d_mc(dst, &tmK, fb, 0, kvrow, bh, (uint16_t)3);
                        tma_load_3d_mc(dst + 16384, &tmK, fb, 64, kvrow, bh, (uint16_t)3);
                    }
                    mbar_wait(bars + 8 * (B_VE + s), ph);
                    {
                        const uint32_t fb = bars + 8 * (B_VF + s);
                        mbar_expect_tx(fb, TILE_BYTES);
                        const uint32_t dst = sbase + SM_V + s * TILE_BYTES + cta_rank * 8192;
                        tma_load_3d_mc(dst, &tmV, fb, 0, kvrow, bh, (uint16_t)3);
                        tma_load_3d_mc(dst + 16384, &tmV, fb, 64, kvrow, bh, (uint16_t)3);
                    }
                    kv_cnt++;
                }
            }
        }
    } else {
        asm volatile("setmaxnreg.inc.sync.aligned.u32 240;");
        const int w = wg - 1;
        const int lane = tid & 31;
        const int warp = (tid >> 5) & 3;
        const int my_bar = 1 + w, other_bar = 1 + (w ^ 1);
        const int epi_bar = 3 + w;
        const float c = 0.08838834764831845f * 1.4426950408889634f;

        float o[64], s[64];
        uint32_t p[32];
        float m0, m1, l0, l1;

        if (w == 1) bar_arrive(1, 256);

        auto release_kv = [&](uint32_t bar) {
            if (lane == 0) {
                mbar_arrive_cluster(bar, 0);
                mbar_arrive_cluster(bar, 1);
            }
        };

        uint32_t kcnt = 0, vcnt = 0;

        auto epilogue = [&](int item) {
            float s0 = l0, s1 = l1;
            s0 += __shfl_xor_sync(0xffffffffu, s0, 1);
            s1 += __shfl_xor_sync(0xffffffffu, s1, 1);
            s0 += __shfl_xor_sync(0xffffffffu, s0, 2);
            s1 += __shfl_xor_sync(0xffffffffu, s1, 2);
            const float r0 = 1.0f / s0, r1 = 1.0f / s1;
            const uint32_t obase = sbase + SM_O + w * 16384;
            if ((tid & 127) == 0) asm volatile("cp.async.bulk.wait_group.read 0;" ::: "memory");
            bar_sync(epi_bar, 128);
            const int mat = lane >> 3, r = lane & 7;
            const int row = warp * 16 + (mat & 1) * 8 + r;
#pragma unroll
            for (int i = 0; i < 8; i++) {
                uint32_t v0 = pack_bf16(o[8 * i] * r0, o[8 * i + 1] * r0);
                uint32_t v1 = pack_bf16(o[8 * i + 2] * r1, o[8 * i + 3] * r1);
                uint32_t v2 = pack_bf16(o[8 * i + 4] * r0, o[8 * i + 5] * r0);
                uint32_t v3 = pack_bf16(o[8 * i + 6] * r1, o[8 * i + 7] * r1);
                const int chunk = 2 * i + (mat >> 1);
                const uint32_t addr = obase + (chunk >> 3) * 8192 + row * 128 + (((chunk & 7) ^ r) << 4);
                asm volatile("stmatrix.sync.aligned.m8n8.x4.shared.b16 [%0], {%1, %2, %3, %4};" ::"r"(addr), "r"(v0),
                             "r"(v1), "r"(v2), "r"(v3)
                             : "memory");
            }
            asm volatile("fence.proxy.async.shared::cta;" ::: "memory");
            bar_sync(epi_bar, 128);
            if ((tid & 127) == 0) {
                const int bh = item >> 2;
                const int row0 = (item & 3) * 256 + (int)cta_rank * 128 + w * 64;
                tma_store_3d(&tmO, obase, 0, row0, bh);
                tma_store_3d(&tmO, obase + 8192, 64, row0, bh);
                asm volatile("cp.async.bulk.commit_group;" ::: "memory");
            }
        };

        {
            mbar_wait(bars + 8 * (B_QF + 0), 0);
            mbar_wait(bars + 8 * (B_KF + 0), 0);
            bar_sync(my_bar, 256);
            wgmma_fence();
            issue_qk(s, sbase + SM_Q + w * 8192, sbase + SM_K);
            wgmma_commit();
            bar_arrive(other_bar, 256);
            wgmma_wait<0>();
            fence_regs(s);
            release_kv(bars + 8 * (B_KE + 0));
            kcnt = 1;
            row_max(s, m0, m1);
            row_exp(s, m0 * c, m1 * c, c, l0, l1);
            pack_p(s, p);
        }

        for (int it = 0; it < my_items; it++) {
            const uint32_t qaddr = sbase + SM_Q + (it & 1) * TILE_BYTES + w * 8192;
#pragma unroll
            for (int n = 1; n < NBLK; n++) {
                const uint32_t ks = kcnt & 1, vs = vcnt & 1;
                mbar_wait(bars + 8 * (B_KF + ks), (kcnt >> 1) & 1);
                bar_sync(my_bar, 256);
                wgmma_fence();
                issue_qk(s, qaddr, sbase + SM_K + ks * TILE_BYTES);
                wgmma_commit();
                mbar_wait(bars + 8 * (B_VF + vs), (vcnt >> 1) & 1);
                wgmma_fence();
                issue_pv(o, p, sbase + SM_V + vs * TILE_BYTES, n == 1 ? 0 : 1);
                wgmma_commit();
                bar_arrive(other_bar, 256);
                wgmma_wait<1>();
                fence_regs(s);
                release_kv(bars + 8 * (B_KE + ks));
                kcnt++;
                if (n == NBLK - 1 && lane == 0) mbar_arrive_local(bars + 8 * (B_QE + (it & 1)));
                float mx0, mx1, sum0, sum1;
                row_max(s, mx0, mx1);
                mx0 = fmaxf(mx0, m0);
                mx1 = fmaxf(mx1, m1);
                const float a0 = ex2((m0 - mx0) * c), a1 = ex2((m1 - mx1) * c);
                m0 = mx0;
                m1 = mx1;
                row_exp(s, mx0 * c, mx1 * c, c, sum0, sum1);
                l0 = l0 * a0 + sum0;
                l1 = l1 * a1 + sum1;
                wgmma_wait<0>();
                fence_regs(o);
                fence_regs_u(p);
                release_kv(bars + 8 * (B_VE + vs));
                vcnt++;
#pragma unroll
                for (int i = 0; i < 16; i++) {
                    o[4 * i] *= a0;
                    o[4 * i + 1] *= a0;
                    o[4 * i + 2] *= a1;
                    o[4 * i + 3] *= a1;
                }
                pack_p(s, p);
            }
            const int item = cluster_id + it * n_clusters;
            const uint32_t vs = vcnt & 1;
            if (it + 1 < my_items) {
                const uint32_t ks = kcnt & 1;
                const int nq = (it + 1) & 1;
                mbar_wait(bars + 8 * (B_QF + nq), ((it + 1) >> 1) & 1);
                mbar_wait(bars + 8 * (B_KF + ks), (kcnt >> 1) & 1);
                bar_sync(my_bar, 256);
                wgmma_fence();
                issue_qk(s, sbase + SM_Q + nq * TILE_BYTES + w * 8192, sbase + SM_K + ks * TILE_BYTES);
                wgmma_commit();
                mbar_wait(bars + 8 * (B_VF + vs), (vcnt >> 1) & 1);
                wgmma_fence();
                issue_pv(o, p, sbase + SM_V + vs * TILE_BYTES, 1);
                wgmma_commit();
                bar_arrive(other_bar, 256);
                wgmma_wait<1>();
                fence_regs(s);
                release_kv(bars + 8 * (B_KE + ks));
                kcnt++;
                float n0, n1, t0, t1;
                row_max(s, n0, n1);
                row_exp(s, n0 * c, n1 * c, c, t0, t1);
                wgmma_wait<0>();
                fence_regs(o);
                fence_regs_u(p);
                release_kv(bars + 8 * (B_VE + vs));
                vcnt++;
                epilogue(item);
                pack_p(s, p);
                m0 = n0;
                m1 = n1;
                l0 = t0;
                l1 = t1;
            } else {
                mbar_wait(bars + 8 * (B_VF + vs), (vcnt >> 1) & 1);
                bar_sync(my_bar, 256);
                wgmma_fence();
                issue_pv(o, p, sbase + SM_V + vs * TILE_BYTES, 1);
                wgmma_commit();
                bar_arrive(other_bar, 256);
                wgmma_wait<0>();
                fence_regs(o);
                release_kv(bars + 8 * (B_VE + vs));
                vcnt++;
                epilogue(item);
            }
        }
        if ((tid & 127) == 0) asm volatile("cp.async.bulk.wait_group 0;" ::: "memory");
    }
    __syncwarp();
    asm volatile("barrier.cluster.arrive.release.aligned;\nbarrier.cluster.wait.acquire.aligned;" ::: "memory");
}

typedef CUresult (*PFN_encodeTiled)(CUtensorMap*, CUtensorMapDataType, cuuint32_t, void*, const cuuint64_t*,
                                    const cuuint64_t*, const cuuint32_t*, const cuuint32_t*, CUtensorMapInterleave,
                                    CUtensorMapSwizzle, CUtensorMapL2promotion, CUtensorMapFloatOOBfill);

bool make_map(PFN_encodeTiled enc, CUtensorMap* tm, const void* ptr, int rows, int box_rows) {
    cuuint64_t dims[3] = {(cuuint64_t)HD, (cuuint64_t)rows, (cuuint64_t)NBH};
    cuuint64_t strides[2] = {(cuuint64_t)HD * 2, (cuuint64_t)rows * HD * 2};
    cuuint32_t box[3] = {64, (cuuint32_t)box_rows, 1};
    cuuint32_t estr[3] = {1, 1, 1};
    return enc(tm, CU_TENSOR_MAP_DATA_TYPE_BFLOAT16, 3, const_cast<void*>(ptr), dims, strides, box, estr,
               CU_TENSOR_MAP_INTERLEAVE_NONE, CU_TENSOR_MAP_SWIZZLE_128B, CU_TENSOR_MAP_L2_PROMOTION_L2_256B,
               CU_TENSOR_MAP_FLOAT_OOB_FILL_NONE) == CUDA_SUCCESS;
}

}

extern "C" void kernel_launch(void* const* d_in, const int* in_sizes, int n_in, void* d_out, int out_size) {
    static PFN_encodeTiled enc = nullptr;
    static int grid = 0;
    if (!enc) {
        void* fn = nullptr;
        cudaDriverEntryPointQueryResult qres;
        cudaGetDriverEntryPoint("cuTensorMapEncodeTiled", &fn, cudaEnableDefault, &qres);
        enc = (PFN_encodeTiled)fn;
        cudaFuncSetAttribute(gqa_attn_kernel, cudaFuncAttributeMaxDynamicSharedMemorySize, SMEM_BYTES);
        int dev = 0, sms = 0;
        cudaGetDevice(&dev);
        cudaDeviceGetAttribute(&sms, cudaDevAttrMultiProcessorCount, dev);
        grid = sms & ~1;
    }
    CUtensorMap tmQ, tmK, tmV, tmO;
    make_map(enc, &tmQ, d_in[0], QROWS, 128);
    make_map(enc, &tmK, d_in[1], SK, 64);
    make_map(enc, &tmV, d_in[2], SK, 64);
    make_map(enc, &tmO, d_out, QROWS, 64);
    gqa_attn_kernel<<<grid, NTHREADS, SMEM_BYTES>>>(tmQ, tmK, tmV, tmO);
}
```

```cpp
#include <cuda_runtime.h>
#include <cuda_bf16.h>
#include <cuda.h>
#include <stdint.h>
#include <type_traits>

#define TL(tag)

namespace {

constexpr int HD = 128;
constexpr int QROWS = 992;
constexpr int SK = 512;
constexpr int NBH = 256;
constexpr int BN = 128;
constexpr int NBLK = SK / BN;
constexpr int NTILES = NBH * 8;

constexpr int TILE_BYTES = 128 * 128 * 2;
constexpr int NST = 5;
constexpr int SM_Q = 0;
constexpr int SM_KV = 2 * TILE_BYTES;
constexpr int SM_BAR = (2 + NST) * TILE_BYTES;
constexpr int SMEM_BYTES = SM_BAR + 256 + 1024;

constexpr int NTHREADS = 384;
constexpr float BIG = 1024.0f;

enum { B_QF = 0, B_QE = 2, B_F = 4, B_E = 4 + NST, B_NUM = 4 + 2 * NST };

__device__ __forceinline__ uint32_t smem_u32(const void* p) {
    return (uint32_t)__cvta_generic_to_shared(p);
}
__device__ __forceinline__ void mbar_init(uint32_t bar, uint32_t count) {
    asm volatile("mbarrier.init.shared::cta.b64 [%0], %1;" ::"r"(bar), "r"(count) : "memory");
}
__device__ __forceinline__ void mbar_expect_tx(uint32_t bar, uint32_t bytes) {
    asm volatile("mbarrier.arrive.expect_tx.shared::cta.b64 _, [%0], %1;" ::"r"(bar), "r"(bytes) : "memory");
}
__device__ __forceinline__ void mbar_wait(uint32_t bar, uint32_t parity) {
    uint32_t ok;
    do {
        asm volatile(
            "{\n"
            ".reg .pred p;\n"
            "mbarrier.try_wait.parity.shared::cta.b64 p, [%1], %2;\n"
            "selp.u32 %0, 1, 0, p;\n"
            "}\n"
            : "=r"(ok)
            : "r"(bar), "r"(parity)
            : "memory");
    } while (!ok);
}
__device__ __forceinline__ void mbar_arrive(uint32_t bar) {
    asm volatile("mbarrier.arrive.shared::cta.b64 _, [%0];" ::"r"(bar) : "memory");
}
__device__ __forceinline__ void tma_load_3d(uint32_t dst, const CUtensorMap* tm, uint32_t bar, int c0, int c1,
                                            int c2) {
    asm volatile(
        "cp.async.bulk.tensor.3d.shared::cluster.global.mbarrier::complete_tx::bytes [%0], [%1, {%3, %4, %5}], "
        "[%2];" ::"r"(dst),
        "l"(tm), "r"(bar), "r"(c0), "r"(c1), "r"(c2)
        : "memory");
}
__device__ __forceinline__ void tma_store_3d(const CUtensorMap* tm, uint32_t src, int c0, int c1, int c2) {
    asm volatile("cp.async.bulk.tensor.3d.global.shared::cta.bulk_group [%0, {%2, %3, %4}], [%1];" ::"l"(tm),
                 "r"(src), "r"(c0), "r"(c1), "r"(c2)
                 : "memory");
}
__device__ __forceinline__ void bar_sync(int id, int n) {
    asm volatile("bar.sync %0, %1;" ::"r"(id), "r"(n) : "memory");
}
__device__ __forceinline__ void bar_arrive(int id, int n) {
    asm volatile("bar.arrive %0, %1;" ::"r"(id), "r"(n) : "memory");
}
__device__ __forceinline__ void wgmma_fence() { asm volatile("wgmma.fence.sync.aligned;" ::: "memory"); }
__device__ __forceinline__ void wgmma_commit() { asm volatile("wgmma.commit_group.sync.aligned;" ::: "memory"); }
template <int N>
__device__ __forceinline__ void wgmma_wait() {
    asm volatile("wgmma.wait_group.sync.aligned %0;" ::"n"(N) : "memory");
}
__device__ __forceinline__ void fence_regs(float (&d)[64]) {
#pragma unroll
    for (int i = 0; i < 64; i++) asm volatile("" : "+f"(d[i])::"memory");
}
__device__ __forceinline__ void fence_regs_u(uint32_t (&d)[32]) {
#pragma unroll
    for (int i = 0; i < 32; i++) asm volatile("" : "+r"(d[i])::"memory");
}

__device__ __forceinline__ uint64_t make_desc(uint32_t addr, uint32_t lbo_bytes, uint32_t sbo_bytes) {
    uint64_t d = 0;
    d |= (uint64_t)((addr & 0x3FFFF) >> 4);
    d |= (uint64_t)(lbo_bytes >> 4) << 16;
    d |= (uint64_t)(sbo_bytes >> 4) << 32;
    d |= (uint64_t)1 << 62;
    return d;
}

#define ACC64(d)                                                                                                       \
    "+f"(d[0]), "+f"(d[1]), "+f"(d[2]), "+f"(d[3]), "+f"(d[4]), "+f"(d[5]), "+f"(d[6]), "+f"(d[7]), "+f"(d[8]),        \
        "+f"(d[9]), "+f"(d[10]), "+f"(d[11]), "+f"(d[12]), "+f"(d[13]), "+f"(d[14]), "+f"(d[15]), "+f"(d[16]),         \
        "+f"(d[17]), "+f"(d[18]), "+f"(d[19]), "+f"(d[20]), "+f"(d[21]), "+f"(d[22]), "+f"(d[23]), "+f"(d[24]),        \
        "+f"(d[25]), "+f"(d[26]), "+f"(d[27]), "+f"(d[28]), "+f"(d[29]), "+f"(d[30]), "+f"(d[31]), "+f"(d[32]),        \
        "+f"(d[33]), "+f"(d[34]), "+f"(d[35]), "+f"(d[36]), "+f"(d[37]), "+f"(d[38]), "+f"(d[39]), "+f"(d[40]),        \
        "+f"(d[41]), "+f"(d[42]), "+f"(d[43]), "+f"(d[44]), "+f"(d[45]), "+f"(d[46]), "+f"(d[47]), "+f"(d[48]),        \
        "+f"(d[49]), "+f"(d[50]), "+f"(d[51]), "+f"(d[52]), "+f"(d[53]), "+f"(d[54]), "+f"(d[55]), "+f"(d[56]),        \
        "+f"(d[57]), "+f"(d[58]), "+f"(d[59]), "+f"(d[60]), "+f"(d[61]), "+f"(d[62]), "+f"(d[63])

#define ACC64_STR                                                                                                      \
    "{%0, %1, %2, %3, %4, %5, %6, %7, %8, %9, %10, %11, %12, %13, %14, %15, %16, %17, %18, %19, %20, %21, %22, %23, "  \
    "%24, %25, %26, %27, %28, %29, %30, %31, %32, %33, %34, %35, %36, %37, %38, %39, %40, %41, %42, %43, %44, %45, "   \
    "%46, %47, %48, %49, %50, %51, %52, %53, %54, %55, %56, %57, %58, %59, %60, %61, %62, %63}"

template <int SCALE_D>
__device__ __forceinline__ void wgmma_ss(float (&d)[64], uint64_t da, uint64_t db) {
    asm volatile(
        "{\n"
        "wgmma.mma_async.sync.aligned.m64n128k16.f32.bf16.bf16 " ACC64_STR
        ", %64, %65, %66, 1, 1, 0, 0;\n"
        "}\n"
        : ACC64(d)
        : "l"(da), "l"(db), "n"(SCALE_D));
}
template <int SCALE_D>
__device__ __forceinline__ void wgmma_rs(float (&d)[64], uint32_t a0, uint32_t a1, uint32_t a2, uint32_t a3,
                                         uint64_t db) {
    asm volatile(
        "{\n"
        "wgmma.mma_async.sync.aligned.m64n128k16.f32.bf16.bf16 " ACC64_STR
        ", {%64, %65, %66, %67}, %68, %69, 1, 1, 1;\n"
        "}\n"
        : ACC64(d)
        : "r"(a0), "r"(a1), "r"(a2), "r"(a3), "l"(db), "n"(SCALE_D));
}

__device__ __forceinline__ float ex2(float x) {
    float y;
    asm("ex2.approx.ftz.f32 %0, %1;" : "=f"(y) : "f"(x));
    return y;
}
__device__ __forceinline__ uint32_t pack_bf16(float lo, float hi) {
    uint32_t r;
    asm("cvt.rn.bf16x2.f32 %0, %1, %2;" : "=r"(r) : "f"(hi), "f"(lo));
    return r;
}

__device__ __forceinline__ void issue_qk(float (&s)[64], uint32_t q_addr, uint32_t k_addr) {
    uint64_t da = make_desc(q_addr, 16, 1024);
    uint64_t db = make_desc(k_addr, 16, 1024);
#pragma unroll
    for (int kk = 0; kk < 8; kk++) {
        uint64_t off = (uint64_t)(((kk >> 2) * 16384 + (kk & 3) * 32) >> 4);
        if (kk == 0)
            wgmma_ss<0>(s, da + off, db + off);
        else
            wgmma_ss<1>(s, da + off, db + off);
    }
}
template <bool INIT>
__device__ __forceinline__ void issue_pv(float (&o)[64], uint32_t (&p)[32], uint32_t v_addr) {
    const uint64_t dv = make_desc(v_addr, 16384, 1024);
#pragma unroll
    for (int kk = 0; kk < 8; kk++) {
        const uint64_t d = dv + (uint64_t)((kk * 2048) >> 4);
        if (INIT && kk == 0)
            wgmma_rs<0>(o, p[4 * kk], p[4 * kk + 1], p[4 * kk + 2], p[4 * kk + 3], d);
        else
            wgmma_rs<1>(o, p[4 * kk], p[4 * kk + 1], p[4 * kk + 2], p[4 * kk + 3], d);
    }
}
__device__ __forceinline__ void exp_pack(const float (&s)[64], uint32_t (&p)[32], float m0c, float m1c, float c,
                                         float& sum0, float& sum1) {
    float x0 = 0.f, x1 = 0.f, y0 = 0.f, y1 = 0.f;
#pragma unroll
    for (int I = 0; I < 16; I++) {
        const float e0 = ex2(fmaf(s[4 * I], c, -m0c));
        const float e1 = ex2(fmaf(s[4 * I + 1], c, -m0c));
        const float e2 = ex2(fmaf(s[4 * I + 2], c, -m1c));
        const float e3 = ex2(fmaf(s[4 * I + 3], c, -m1c));
        x0 += e0;
        y0 += e1;
        x1 += e2;
        y1 += e3;
        p[2 * I] = pack_bf16(e0, e1);
        p[2 * I + 1] = pack_bf16(e2, e3);
    }
    sum0 = x0 + y0;
    sum1 = x1 + y1;
}
__device__ __forceinline__ void row_max(const float (&s)[64], float& mx0, float& mx1) {
    float a0 = fmaxf(s[0], s[1]), a1 = fmaxf(s[2], s[3]);
    float b0 = fmaxf(s[4], s[5]), b1 = fmaxf(s[6], s[7]);
#pragma unroll
    for (int i = 2; i < 16; i += 2) {
        a0 = fmaxf(a0, fmaxf(s[4 * i], s[4 * i + 1]));
        a1 = fmaxf(a1, fmaxf(s[4 * i + 2], s[4 * i + 3]));
        b0 = fmaxf(b0, fmaxf(s[4 * i + 4], s[4 * i + 5]));
        b1 = fmaxf(b1, fmaxf(s[4 * i + 6], s[4 * i + 7]));
    }
    mx0 = fmaxf(a0, b0);
    mx1 = fmaxf(a1, b1);
    mx0 = fmaxf(mx0, __shfl_xor_sync(0xffffffffu, mx0, 1));
    mx1 = fmaxf(mx1, __shfl_xor_sync(0xffffffffu, mx1, 1));
    mx0 = fmaxf(mx0, __shfl_xor_sync(0xffffffffu, mx0, 2));
    mx1 = fmaxf(mx1, __shfl_xor_sync(0xffffffffu, mx1, 2));
}

__global__ void __launch_bounds__(NTHREADS, 1)
    gqa_attn_kernel(const __grid_constant__ CUtensorMap tmQ, const __grid_constant__ CUtensorMap tmK,
                    const __grid_constant__ CUtensorMap tmV, const __grid_constant__ CUtensorMap tmO) {
    extern __shared__ uint8_t smem_raw[];
    const uint32_t sbase = (smem_u32(smem_raw) + 1023u) & ~1023u;
    const uint32_t bars = sbase + SM_BAR;
    const int tid = threadIdx.x;
    const int wg = tid >> 7;
    const int cta = blockIdx.x;
    const int ncta = gridDim.x;
    const int my_tiles = (NTILES - cta + ncta - 1) / ncta;

    if (tid == 0) {
        for (int s = 0; s < 2; s++) {
            mbar_init(bars + 8 * (B_QF + s), 1);
            mbar_init(bars + 8 * (B_QE + s), 2);
        }
        for (int s = 0; s < NST; s++) {
            mbar_init(bars + 8 * (B_F + s), 1);
            mbar_init(bars + 8 * (B_E + s), 8);
        }
        asm volatile("fence.mbarrier_init.release.cluster;" ::: "memory");
    }
    __syncthreads();

    if (wg == 0) {
        asm volatile("setmaxnreg.dec.sync.aligned.u32 24;");
        if (tid == 0) {
            asm volatile("prefetch.tensormap [%0];" ::"l"(&tmQ) : "memory");
            asm volatile("prefetch.tensormap [%0];" ::"l"(&tmK) : "memory");
            asm volatile("prefetch.tensormap [%0];" ::"l"(&tmV) : "memory");
            uint32_t st = 0, ph = 1;
            auto load_kv = [&](const CUtensorMap* tm, int blk, int bh) {
                mbar_wait(bars + 8 * (B_E + st), ph);
                const uint32_t fb = bars + 8 * (B_F + st);
                mbar_expect_tx(fb, TILE_BYTES);
                const uint32_t dst = sbase + SM_KV + st * TILE_BYTES;
                tma_load_3d(dst, tm, fb, 0, blk * BN, bh);
                tma_load_3d(dst + 16384, tm, fb, 64, blk * BN, bh);
                if (++st == NST) {
                    st = 0;
                    ph ^= 1;
                }
            };
            auto load_q = [&](int it) {
                const int tile = cta + it * ncta;
                const int qs = it & 1;
                mbar_wait(bars + 8 * (B_QE + qs), ((it >> 1) & 1) ^ 1);
                const uint32_t fb = bars + 8 * (B_QF + qs);
                mbar_expect_tx(fb, TILE_BYTES);
                const uint32_t dst = sbase + SM_Q + qs * TILE_BYTES;
                tma_load_3d(dst, &tmQ, fb, 0, (tile & 7) * 128, tile >> 3);
                tma_load_3d(dst + 16384, &tmQ, fb, 64, (tile & 7) * 128, tile >> 3);
            };
            load_q(0);
            load_kv(&tmK, 0, cta >> 3);
            for (int it = 0; it < my_tiles; it++) {
                const int bh = (cta + it * ncta) >> 3;
                for (int n = 1; n < NBLK; n++) {
                    load_kv(&tmK, n, bh);
                    load_kv(&tmV, n - 1, bh);
                }
                if (it + 1 < my_tiles) {
                    load_q(it + 1);
                    load_kv(&tmK, 0, (cta + (it + 1) * ncta) >> 3);
                }
                load_kv(&tmV, NBLK - 1, bh);
            }
        }
    } else {
        asm volatile("setmaxnreg.inc.sync.aligned.u32 240;");
        const int w = wg - 1;
        const int lane = tid & 31;
        const int warp = (tid >> 5) & 3;
        const int my_bar = 1 + w, other_bar = 1 + (w ^ 1);
        const int epi_bar = 3 + w;
        const float c = 0.08838834764831845f * 1.4426950408889634f;

        float o[64], s[64];
        uint32_t p[32];
        float m0, m1, l0, l1;

        if (w == 1) bar_arrive(1, 256);

        auto release_kv = [&](uint32_t stage) {
            if (lane == 0) mbar_arrive(bars + 8 * (B_E + stage));
        };
        uint32_t st = 0, ph = 0;
        auto advance = [&]() {
            if (++st == NST) {
                st = 0;
                ph ^= 1;
            }
        };

        auto epilogue = [&](int tile, uint32_t obase) {
            float s0 = l0, s1 = l1;
            s0 += __shfl_xor_sync(0xffffffffu, s0, 1);
            s1 += __shfl_xor_sync(0xffffffffu, s1, 1);
            s0 += __shfl_xor_sync(0xffffffffu, s0, 2);
            s1 += __shfl_xor_sync(0xffffffffu, s1, 2);
            const float r0 = 1.0f / s0, r1 = 1.0f / s1;
            const int mat = lane >> 3, r = lane & 7;
            const int row = warp * 16 + (mat & 1) * 8 + r;
#pragma unroll
            for (int i = 0; i < 8; i++) {
                uint32_t v0 = pack_bf16(o[8 * i] * r0, o[8 * i + 1] * r0);
                uint32_t v1 = pack_bf16(o[8 * i + 2] * r1, o[8 * i + 3] * r1);
                uint32_t v2 = pack_bf16(o[8 * i + 4] * r0, o[8 * i + 5] * r0);
                uint32_t v3 = pack_bf16(o[8 * i + 6] * r1, o[8 * i + 7] * r1);
                const int chunk = 2 * i + (mat >> 1);
                const uint32_t addr = obase + (chunk >> 3) * 16384 + row * 128 + (((chunk & 7) ^ r) << 4);
                asm volatile("stmatrix.sync.aligned.m8n8.x4.shared.b16 [%0], {%1, %2, %3, %4};" ::"r"(addr), "r"(v0),
                             "r"(v1), "r"(v2), "r"(v3)
                             : "memory");
            }
            asm volatile("fence.proxy.async.shared::cta;" ::: "memory");
            bar_sync(epi_bar, 128);
            if ((tid & 127) == 0) {
                const int row0 = (tile & 7) * 128 + w * 64;
                tma_store_3d(&tmO, obase, 0, row0, tile >> 3);
                tma_store_3d(&tmO, obase + 16384, 64, row0, tile >> 3);
                asm volatile("cp.async.bulk.commit_group;" ::: "memory");
            }
        };

        {
            mbar_wait(bars + 8 * (B_QF + 0), 0);
            mbar_wait(bars + 8 * (B_F + 0), 0);
            bar_sync(my_bar, 256);
            wgmma_fence();
            issue_qk(s, sbase + SM_Q + w * 8192, sbase + SM_KV);
            wgmma_commit();
            bar_arrive(other_bar, 256);
            wgmma_wait<0>();
            fence_regs(s);
            release_kv(0);
            advance();
            row_max(s, m0, m1);
            exp_pack(s, p, m0 * c, m1 * c, c, l0, l1);
            fence_regs_u(p);
        }

        auto step = [&](auto new_tile_c, auto pv_init_c, auto rel_q_c, uint32_t qaddr, uint32_t aux, int tile) {
            constexpr bool NEW_TILE = decltype(new_tile_c)::value;
            constexpr bool PV_INIT = decltype(pv_init_c)::value;
            constexpr bool REL_Q = decltype(rel_q_c)::value;
            const uint32_t ks = st, kph = ph;
            advance();
            const uint32_t vs = st, vph = ph;
            advance();
            TL(0);
            mbar_wait(bars + 8 * (B_F + ks), kph);
            mbar_wait(bars + 8 * (B_F + vs), vph);
            TL(1);
            bar_sync(my_bar, 256);
            TL(8);
            wgmma_fence();
            issue_pv<PV_INIT>(o, p, sbase + SM_KV + vs * TILE_BYTES);
            wgmma_commit();
            issue_qk(s, qaddr, sbase + SM_KV + ks * TILE_BYTES);
            wgmma_commit();
            bar_arrive(other_bar, 256);
            TL(2);
            wgmma_wait<1>();
            TL(3);
            fence_regs(o);
            fence_regs_u(p);
            release_kv(vs);
            if (REL_Q && (tid & 127) == 0) {
                asm volatile("cp.async.bulk.wait_group.read 0;" ::: "memory");
                mbar_arrive(aux);
            }
            if (NEW_TILE) epilogue(tile, aux);
            TL(4);
            wgmma_wait<0>();
            TL(5);
            fence_regs(s);
            release_kv(ks);
            if (NEW_TILE) {
                row_max(s, m0, m1);
                exp_pack(s, p, m0 * c, m1 * c, c, l0, l1);
            } else {
                float sum0, sum1;
                exp_pack(s, p, m0 * c, m1 * c, c, sum0, sum1);
                if (__any_sync(0xffffffffu, !(sum0 <= BIG && sum1 <= BIG))) {
                    float mx0, mx1;
                    row_max(s, mx0, mx1);
                    mx0 = fmaxf(mx0, m0);
                    mx1 = fmaxf(mx1, m1);
                    const float a0 = ex2((m0 - mx0) * c), a1 = ex2((m1 - mx1) * c);
                    m0 = mx0;
                    m1 = mx1;
                    l0 *= a0;
                    l1 *= a1;
#pragma unroll
                    for (int i = 0; i < 16; i++) {
                        o[4 * i] *= a0;
                        o[4 * i + 1] *= a0;
                        o[4 * i + 2] *= a1;
                        o[4 * i + 3] *= a1;
                    }
                    exp_pack(s, p, m0 * c, m1 * c, c, sum0, sum1);
                }
                l0 += sum0;
                l1 += sum1;
            }
            TL(7);
        };
        using T_ = std::true_type;
        using F_ = std::false_type;

        for (int it = 0; it < my_tiles; it++) {
            const uint32_t qaddr = sbase + SM_Q + (it & 1) * TILE_BYTES + w * 8192;
            const int tile = cta + it * ncta;
            step(F_{}, T_{}, F_{}, qaddr, 0u, tile);
            if (it > 0)
                step(F_{}, F_{}, T_{}, qaddr, bars + 8 * (B_QE + ((it - 1) & 1)), tile);
            else
                step(F_{}, F_{}, F_{}, qaddr, 0u, tile);
            step(F_{}, F_{}, F_{}, qaddr, 0u, tile);
            if (it + 1 < my_tiles) {
                const int nq = (it + 1) & 1;
                mbar_wait(bars + 8 * (B_QF + nq), ((it + 1) >> 1) & 1);
                step(T_{}, F_{}, F_{}, sbase + SM_Q + nq * TILE_BYTES + w * 8192, qaddr, tile);
            } else {
                const uint32_t vs = st;
                mbar_wait(bars + 8 * (B_F + vs), ph);
                bar_sync(my_bar, 256);
                wgmma_fence();
                issue_pv<false>(o, p, sbase + SM_KV + vs * TILE_BYTES);
                wgmma_commit();
                bar_arrive(other_bar, 256);
                wgmma_wait<0>();
                fence_regs(o);
                release_kv(vs);
                epilogue(tile, qaddr);
            }
        }
        if ((tid & 127) == 0) asm volatile("cp.async.bulk.wait_group 0;" ::: "memory");
    }
}

typedef CUresult (*PFN_encodeTiled)(CUtensorMap*, CUtensorMapDataType, cuuint32_t, void*, const cuuint64_t*,
                                    const cuuint64_t*, const cuuint32_t*, const cuuint32_t*, CUtensorMapInterleave,
                                    CUtensorMapSwizzle, CUtensorMapL2promotion, CUtensorMapFloatOOBfill);

bool make_map(PFN_encodeTiled enc, CUtensorMap* tm, const void* ptr, int rows, int box_rows) {
    cuuint64_t dims[3] = {(cuuint64_t)HD, (cuuint64_t)rows, (cuuint64_t)NBH};
    cuuint64_t strides[2] = {(cuuint64_t)HD * 2, (cuuint64_t)rows * HD * 2};
    cuuint32_t box[3] = {64, (cuuint32_t)box_rows, 1};
    cuuint32_t estr[3] = {1, 1, 1};
    return enc(tm, CU_TENSOR_MAP_DATA_TYPE_BFLOAT16, 3, const_cast<void*>(ptr), dims, strides, box, estr,
               CU_TENSOR_MAP_INTERLEAVE_NONE, CU_TENSOR_MAP_SWIZZLE_128B, CU_TENSOR_MAP_L2_PROMOTION_L2_256B,
               CU_TENSOR_MAP_FLOAT_OOB_FILL_NONE) == CUDA_SUCCESS;
}

}

extern "C" void kernel_launch(void* const* d_in, const int* in_sizes, int n_in, void* d_out, int out_size) {
    static PFN_encodeTiled enc = nullptr;
    static int grid = 0;
    if (!enc) {
        void* fn = nullptr;
        cudaDriverEntryPointQueryResult qres;
        cudaGetDriverEntryPoint("cuTensorMapEncodeTiled", &fn, cudaEnableDefault, &qres);
        enc = (PFN_encodeTiled)fn;
        cudaFuncSetAttribute(gqa_attn_kernel, cudaFuncAttributeMaxDynamicSharedMemorySize, SMEM_BYTES);
        int dev = 0, sms = 0;
        cudaGetDevice(&dev);
        cudaDeviceGetAttribute(&sms, cudaDevAttrMultiProcessorCount, dev);
        grid = sms;
    }
    CUtensorMap tmQ, tmK, tmV, tmO;
    make_map(enc, &tmQ, d_in[0], QROWS, 128);
    make_map(enc, &tmK, d_in[1], SK, 128);
    make_map(enc, &tmV, d_in[2], SK, 128);
    make_map(enc, &tmO, d_out, QROWS, 64);
    gqa_attn_kernel<<<grid, NTHREADS, SMEM_BYTES>>>(tmQ, tmK, tmV, tmO);
}
```

```cpp
#include <cuda_runtime.h>
#include <cuda_bf16.h>
#include <cuda.h>
#include <stdint.h>
#include <type_traits>

namespace {

constexpr int HD = 128;
constexpr int QROWS = 992;
constexpr int SK = 512;
constexpr int NBH = 256;
constexpr int BN = 128;
constexpr int NBLK = SK / BN;
constexpr int NTILES = NBH * 8;

constexpr int TILE_BYTES = 128 * 128 * 2;
constexpr int NST = 5;
constexpr int SM_Q = 0;
constexpr int SM_KV = 2 * TILE_BYTES;
constexpr int SM_BAR = (2 + NST) * TILE_BYTES;
constexpr int SMEM_BYTES = SM_BAR + 256 + 1024;

constexpr int NTHREADS = 384;
constexpr float BIG = 1024.0f;

enum { B_QF = 0, B_QE = 2, B_F = 4, B_E = 4 + NST, B_NUM = 4 + 2 * NST };

__device__ __forceinline__ uint32_t smem_u32(const void* p) {
    return (uint32_t)__cvta_generic_to_shared(p);
}
__device__ __forceinline__ void mbar_init(uint32_t bar, uint32_t count) {
    asm volatile("mbarrier.init.shared::cta.b64 [%0], %1;" ::"r"(bar), "r"(count) : "memory");
}
__device__ __forceinline__ void mbar_expect_tx(uint32_t bar, uint32_t bytes) {
    asm volatile("mbarrier.arrive.expect_tx.shared::cta.b64 _, [%0], %1;" ::"r"(bar), "r"(bytes) : "memory");
}
__device__ __forceinline__ void mbar_wait(uint32_t bar, uint32_t parity) {
    uint32_t ok;
    do {
        asm volatile(
            "{\n"
            ".reg .pred p;\n"
            "mbarrier.try_wait.parity.shared::cta.b64 p, [%1], %2;\n"
            "selp.u32 %0, 1, 0, p;\n"
            "}\n"
            : "=r"(ok)
            : "r"(bar), "r"(parity)
            : "memory");
    } while (!ok);
}
__device__ __forceinline__ void mbar_arrive(uint32_t bar) {
    asm volatile("mbarrier.arrive.shared::cta.b64 _, [%0];" ::"r"(bar) : "memory");
}
__device__ __forceinline__ void tma_load_3d(uint32_t dst, const CUtensorMap* tm, uint32_t bar, int c0, int c1,
                                            int c2) {
    asm volatile(
        "cp.async.bulk.tensor.3d.shared::cluster.global.mbarrier::complete_tx::bytes [%0], [%1, {%3, %4, %5}], "
        "[%2];" ::"r"(dst),
        "l"(tm), "r"(bar), "r"(c0), "r"(c1), "r"(c2)
        : "memory");
}
__device__ __forceinline__ void tma_store_3d(const CUtensorMap* tm, uint32_t src, int c0, int c1, int c2) {
    asm volatile("cp.async.bulk.tensor.3d.global.shared::cta.bulk_group [%0, {%2, %3, %4}], [%1];" ::"l"(tm),
                 "r"(src), "r"(c0), "r"(c1), "r"(c2)
                 : "memory");
}
__device__ __forceinline__ void bar_sync(int id, int n) {
    asm volatile("bar.sync %0, %1;" ::"r"(id), "r"(n) : "memory");
}
__device__ __forceinline__ void bar_arrive(int id, int n) {
    asm volatile("bar.arrive %0, %1;" ::"r"(id), "r"(n) : "memory");
}
__device__ __forceinline__ void wgmma_fence() { asm volatile("wgmma.fence.sync.aligned;" ::: "memory"); }
__device__ __forceinline__ void wgmma_commit() { asm volatile("wgmma.commit_group.sync.aligned;" ::: "memory"); }
template <int N>
__device__ __forceinline__ void wgmma_wait() {
    asm volatile("wgmma.wait_group.sync.aligned %0;" ::"n"(N) : "memory");
}
__device__ __forceinline__ void fence_regs(float (&d)[64]) {
#pragma unroll
    for (int i = 0; i < 64; i++) asm volatile("" : "+f"(d[i])::"memory");
}
__device__ __forceinline__ void fence_regs_u(uint32_t (&d)[32]) {
#pragma unroll
    for (int i = 0; i < 32; i++) asm volatile("" : "+r"(d[i])::"memory");
}

__device__ __forceinline__ uint64_t make_desc(uint32_t addr, uint32_t lbo_bytes, uint32_t sbo_bytes) {
    uint64_t d = 0;
    d |= (uint64_t)((addr & 0x3FFFF) >> 4);
    d |= (uint64_t)(lbo_bytes >> 4) << 16;
    d |= (uint64_t)(sbo_bytes >> 4) << 32;
    d |= (uint64_t)1 << 62;
    return d;
}

#define ACC64(d)                                                                                                       \
    "+f"(d[0]), "+f"(d[1]), "+f"(d[2]), "+f"(d[3]), "+f"(d[4]), "+f"(d[5]), "+f"(d[6]), "+f"(d[7]), "+f"(d[8]),        \
        "+f"(d[9]), "+f"(d[10]), "+f"(d[11]), "+f"(d[12]), "+f"(d[13]), "+f"(d[14]), "+f"(d[15]), "+f"(d[16]),         \
        "+f"(d[17]), "+f"(d[18]), "+f"(d[19]), "+f"(d[20]), "+f"(d[21]), "+f"(d[22]), "+f"(d[23]), "+f"(d[24]),        \
        "+f"(d[25]), "+f"(d[26]), "+f"(d[27]), "+f"(d[28]), "+f"(d[29]), "+f"(d[30]), "+f"(d[31]), "+f"(d[32]),        \
        "+f"(d[33]), "+f"(d[34]), "+f"(d[35]), "+f"(d[36]), "+f"(d[37]), "+f"(d[38]), "+f"(d[39]), "+f"(d[40]),        \
        "+f"(d[41]), "+f"(d[42]), "+f"(d[43]), "+f"(d[44]), "+f"(d[45]), "+f"(d[46]), "+f"(d[47]), "+f"(d[48]),        \
        "+f"(d[49]), "+f"(d[50]), "+f"(d[51]), "+f"(d[52]), "+f"(d[53]), "+f"(d[54]), "+f"(d[55]), "+f"(d[56]),        \
        "+f"(d[57]), "+f"(d[58]), "+f"(d[59]), "+f"(d[60]), "+f"(d[61]), "+f"(d[62]), "+f"(d[63])

#define ACC64_STR                                                                                                      \
    "{%0, %1, %2, %3, %4, %5, %6, %7, %8, %9, %10, %11, %12, %13, %14, %15, %16, %17, %18, %19, %20, %21, %22, %23, "  \
    "%24, %25, %26, %27, %28, %29, %30, %31, %32, %33, %34, %35, %36, %37, %38, %39, %40, %41, %42, %43, %44, %45, "   \
    "%46, %47, %48, %49, %50, %51, %52, %53, %54, %55, %56, %57, %58, %59, %60, %61, %62, %63}"

template <int SCALE_D>
__device__ __forceinline__ void wgmma_ss(float (&d)[64], uint64_t da, uint64_t db) {
    asm volatile(
        "{\n"
        "wgmma.mma_async.sync.aligned.m64n128k16.f32.bf16.bf16 " ACC64_STR
        ", %64, %65, %66, 1, 1, 0, 0;\n"
        "}\n"
        : ACC64(d)
        : "l"(da), "l"(db), "n"(SCALE_D));
}
template <int SCALE_D>
__device__ __forceinline__ void wgmma_rs(float (&d)[64], uint32_t a0, uint32_t a1, uint32_t a2, uint32_t a3,
                                         uint64_t db) {
    asm volatile(
        "{\n"
        "wgmma.mma_async.sync.aligned.m64n128k16.f32.bf16.bf16 " ACC64_STR
        ", {%64, %65, %66, %67}, %68, %69, 1, 1, 1;\n"
        "}\n"
        : ACC64(d)
        : "r"(a0), "r"(a1), "r"(a2), "r"(a3), "l"(db), "n"(SCALE_D));
}

__device__ __forceinline__ float ex2(float x) {
    float y;
    asm("ex2.approx.ftz.f32 %0, %1;" : "=f"(y) : "f"(x));
    return y;
}
__device__ __forceinline__ uint32_t pack_bf16(float lo, float hi) {
    uint32_t r;
    asm("cvt.rn.bf16x2.f32 %0, %1, %2;" : "=r"(r) : "f"(hi), "f"(lo));
    return r;
}

__device__ __forceinline__ void issue_qk(float (&s)[64], uint32_t q_addr, uint32_t k_addr) {
    uint64_t da = make_desc(q_addr, 16, 1024);
    uint64_t db = make_desc(k_addr, 16, 1024);
#pragma unroll
    for (int kk = 0; kk < 8; kk++) {
        uint64_t off = (uint64_t)(((kk >> 2) * 16384 + (kk & 3) * 32) >> 4);
        if (kk == 0)
            wgmma_ss<0>(s, da + off, db + off);
        else
            wgmma_ss<1>(s, da + off, db + off);
    }
}
template <bool INIT>
__device__ __forceinline__ void issue_pv(float (&o)[64], uint32_t (&p)[32], uint32_t v_addr) {
    const uint64_t dv = make_desc(v_addr, 16384, 1024);
#pragma unroll
    for (int kk = 0; kk < 8; kk++) {
        const uint64_t d = dv + (uint64_t)((kk * 2048) >> 4);
        if (INIT && kk == 0)
            wgmma_rs<0>(o, p[4 * kk], p[4 * kk + 1], p[4 * kk + 2], p[4 * kk + 3], d);
        else
            wgmma_rs<1>(o, p[4 * kk], p[4 * kk + 1], p[4 * kk + 2], p[4 * kk + 3], d);
    }
}
__device__ __forceinline__ void exp_pack(const float (&s)[64], uint32_t (&p)[32], float m0c, float m1c, float c,
                                         float& sum0, float& sum1) {
    float x0 = 0.f, x1 = 0.f, y0 = 0.f, y1 = 0.f;
#pragma unroll
    for (int I = 0; I < 16; I++) {
        const float e0 = ex2(fmaf(s[4 * I], c, -m0c));
        const float e1 = ex2(fmaf(s[4 * I + 1], c, -m0c));
        const float e2 = ex2(fmaf(s[4 * I + 2], c, -m1c));
        const float e3 = ex2(fmaf(s[4 * I + 3], c, -m1c));
        x0 += e0;
        y0 += e1;
        x1 += e2;
        y1 += e3;
        p[2 * I] = pack_bf16(e0, e1);
        p[2 * I + 1] = pack_bf16(e2, e3);
    }
    sum0 = x0 + y0;
    sum1 = x1 + y1;
}
__device__ __forceinline__ void row_max(const float (&s)[64], float& mx0, float& mx1) {
    float a0 = fmaxf(s[0], s[1]), a1 = fmaxf(s[2], s[3]);
    float b0 = fmaxf(s[4], s[5]), b1 = fmaxf(s[6], s[7]);
#pragma unroll
    for (int i = 2; i < 16; i += 2) {
        a0 = fmaxf(a0, fmaxf(s[4 * i], s[4 * i + 1]));
        a1 = fmaxf(a1, fmaxf(s[4 * i + 2], s[4 * i + 3]));
        b0 = fmaxf(b0, fmaxf(s[4 * i + 4], s[4 * i + 5]));
        b1 = fmaxf(b1, fmaxf(s[4 * i + 6], s[4 * i + 7]));
    }
    mx0 = fmaxf(a0, b0);
    mx1 = fmaxf(a1, b1);
    mx0 = fmaxf(mx0, __shfl_xor_sync(0xffffffffu, mx0, 1));
    mx1 = fmaxf(mx1, __shfl_xor_sync(0xffffffffu, mx1, 1));
    mx0 = fmaxf(mx0, __shfl_xor_sync(0xffffffffu, mx0, 2));
    mx1 = fmaxf(mx1, __shfl_xor_sync(0xffffffffu, mx1, 2));
}

__global__ void __launch_bounds__(NTHREADS, 1)
    gqa_attn_kernel(const __grid_constant__ CUtensorMap tmQ, const __grid_constant__ CUtensorMap tmK,
                    const __grid_constant__ CUtensorMap tmV, const __grid_constant__ CUtensorMap tmO) {
    extern __shared__ uint8_t smem_raw[];
    const uint32_t sbase = (smem_u32(smem_raw) + 1023u) & ~1023u;
    const uint32_t bars = sbase + SM_BAR;
    const int tid = threadIdx.x;
    const int wg = tid >> 7;
    const int cta = blockIdx.x;
    const int ncta = gridDim.x;
    const int my_tiles = (NTILES - cta + ncta - 1) / ncta;

    if (tid == 0) {
        for (int s = 0; s < 2; s++) {
            mbar_init(bars + 8 * (B_QF + s), 1);
            mbar_init(bars + 8 * (B_QE + s), 2);
        }
        for (int s = 0; s < NST; s++) {
            mbar_init(bars + 8 * (B_F + s), 1);
            mbar_init(bars + 8 * (B_E + s), 8);
        }
        asm volatile("fence.mbarrier_init.release.cluster;" ::: "memory");
    }
    __syncthreads();

    if (wg == 0) {
        asm volatile("setmaxnreg.dec.sync.aligned.u32 24;");
        if (tid == 0) {
            asm volatile("prefetch.tensormap [%0];" ::"l"(&tmQ) : "memory");
            asm volatile("prefetch.tensormap [%0];" ::"l"(&tmK) : "memory");
            asm volatile("prefetch.tensormap [%0];" ::"l"(&tmV) : "memory");
            uint32_t st = 0, ph = 1;
            auto load_kv = [&](const CUtensorMap* tm, int blk, int bh) {
                mbar_wait(bars + 8 * (B_E + st), ph);
                const uint32_t fb = bars + 8 * (B_F + st);
                mbar_expect_tx(fb, TILE_BYTES);
                const uint32_t dst = sbase + SM_KV + st * TILE_BYTES;
                tma_load_3d(dst, tm, fb, 0, blk * BN, bh);
                tma_load_3d(dst + 16384, tm, fb, 64, blk * BN, bh);
                if (++st == NST) {
                    st = 0;
                    ph ^= 1;
                }
            };
            auto load_q = [&](int it) {
                const int tile = cta + it * ncta;
                const int qs = it & 1;
                mbar_wait(bars + 8 * (B_QE + qs), ((it >> 1) & 1) ^ 1);
                const uint32_t fb = bars + 8 * (B_QF + qs);
                mbar_expect_tx(fb, TILE_BYTES);
                const uint32_t dst = sbase + SM_Q + qs * TILE_BYTES;
                tma_load_3d(dst, &tmQ, fb, 0, (tile & 7) * 128, tile >> 3);
                tma_load_3d(dst + 16384, &tmQ, fb, 64, (tile & 7) * 128, tile >> 3);
            };
            load_q(0);
            load_kv(&tmK, 0, cta >> 3);
            for (int it = 0; it < my_tiles; it++) {
                const int bh = (cta + it * ncta) >> 3;
                for (int n = 1; n < NBLK; n++) {
                    load_kv(&tmK, n, bh);
                    load_kv(&tmV, n - 1, bh);
                }
                if (it + 1 < my_tiles) {
                    load_q(it + 1);
                    load_kv(&tmK, 0, (cta + (it + 1) * ncta) >> 3);
                }
                load_kv(&tmV, NBLK - 1, bh);
            }
        }
    } else {
        asm volatile("setmaxnreg.inc.sync.aligned.u32 240;");
        const int w = wg - 1;
        const int lane = tid & 31;
        const int warp = (tid >> 5) & 3;
        const int my_bar = 1 + w, other_bar = 1 + (w ^ 1);
        const int epi_bar = 3 + w;
        const float c = 0.08838834764831845f * 1.4426950408889634f;

        float o[64], s[64];
        uint32_t p[32];
        float m0, m1, l0, l1;

        if (w == 1) bar_arrive(1, 256);

        auto release_kv = [&](uint32_t stage) {
            if (lane == 0) mbar_arrive(bars + 8 * (B_E + stage));
        };
        uint32_t st = 0, ph = 0;
        auto advance = [&]() {
            if (++st == NST) {
                st = 0;
                ph ^= 1;
            }
        };

        auto epilogue = [&](int tile, uint32_t obase) {
            float s0 = l0, s1 = l1;
            s0 += __shfl_xor_sync(0xffffffffu, s0, 1);
            s1 += __shfl_xor_sync(0xffffffffu, s1, 1);
            s0 += __shfl_xor_sync(0xffffffffu, s0, 2);
            s1 += __shfl_xor_sync(0xffffffffu, s1, 2);
            const float r0 = 1.0f / s0, r1 = 1.0f / s1;
            const int mat = lane >> 3, r = lane & 7;
            const int row = warp * 16 + (mat & 1) * 8 + r;
#pragma unroll
            for (int i = 0; i < 8; i++) {
                uint32_t v0 = pack_bf16(o[8 * i] * r0, o[8 * i + 1] * r0);
                uint32_t v1 = pack_bf16(o[8 * i + 2] * r1, o[8 * i + 3] * r1);
                uint32_t v2 = pack_bf16(o[8 * i + 4] * r0, o[8 * i + 5] * r0);
                uint32_t v3 = pack_bf16(o[8 * i + 6] * r1, o[8 * i + 7] * r1);
                const int chunk = 2 * i + (mat >> 1);
                const uint32_t addr = obase + (chunk >> 3) * 16384 + row * 128 + (((chunk & 7) ^ r) << 4);
                asm volatile("stmatrix.sync.aligned.m8n8.x4.shared.b16 [%0], {%1, %2, %3, %4};" ::"r"(addr), "r"(v0),
                             "r"(v1), "r"(v2), "r"(v3)
                             : "memory");
            }
            asm volatile("fence.proxy.async.shared::cta;" ::: "memory");
            bar_sync(epi_bar, 128);
            if ((tid & 127) == 0) {
                const int row0 = (tile & 7) * 128 + w * 64;
                tma_store_3d(&tmO, obase, 0, row0, tile >> 3);
                tma_store_3d(&tmO, obase + 16384, 64, row0, tile >> 3);
                asm volatile("cp.async.bulk.commit_group;" ::: "memory");
            }
        };

        {
            mbar_wait(bars + 8 * (B_QF + 0), 0);
            mbar_wait(bars + 8 * (B_F + 0), 0);
            bar_sync(my_bar, 256);
            wgmma_fence();
            issue_qk(s, sbase + SM_Q + w * 8192, sbase + SM_KV);
            wgmma_commit();
            bar_arrive(other_bar, 256);
            wgmma_wait<0>();
            fence_regs(s);
            release_kv(0);
            advance();
            row_max(s, m0, m1);
            exp_pack(s, p, m0 * c, m1 * c, c, l0, l1);
            fence_regs_u(p);
        }

        auto step = [&](auto new_tile_c, auto pv_init_c, auto rel_q_c, uint32_t qaddr, uint32_t aux, int tile) {
            constexpr bool NEW_TILE = decltype(new_tile_c)::value;
            constexpr bool PV_INIT = decltype(pv_init_c)::value;
            constexpr bool REL_Q = decltype(rel_q_c)::value;
            const uint32_t ks = st, kph = ph;
            advance();
            const uint32_t vs = st, vph = ph;
            advance();
            mbar_wait(bars + 8 * (B_F + ks), kph);
            mbar_wait(bars + 8 * (B_F + vs), vph);
            bar_sync(my_bar, 256);
            wgmma_fence();
            issue_pv<PV_INIT>(o, p, sbase + SM_KV + vs * TILE_BYTES);
            wgmma_commit();
            issue_qk(s, qaddr, sbase + SM_KV + ks * TILE_BYTES);
            wgmma_commit();
            bar_arrive(other_bar, 256);
            wgmma_wait<1>();
            fence_regs(o);
            fence_regs_u(p);
            release_kv(vs);
            if (REL_Q && (tid & 127) == 0) {
                asm volatile("cp.async.bulk.wait_group.read 0;" ::: "memory");
                mbar_arrive(aux);
            }
            if (NEW_TILE) epilogue(tile, aux);
            wgmma_wait<0>();
            fence_regs(s);
            release_kv(ks);
            if (NEW_TILE) {
                row_max(s, m0, m1);
                exp_pack(s, p, m0 * c, m1 * c, c, l0, l1);
            } else {
                float sum0, sum1;
                exp_pack(s, p, m0 * c, m1 * c, c, sum0, sum1);
                if (__any_sync(0xffffffffu, !(sum0 <= BIG && sum1 <= BIG))) {
                    float mx0, mx1;
                    row_max(s, mx0, mx1);
                    mx0 = fmaxf(mx0, m0);
                    mx1 = fmaxf(mx1, m1);
                    const float a0 = ex2((m0 - mx0) * c), a1 = ex2((m1 - mx1) * c);
                    m0 = mx0;
                    m1 = mx1;
                    l0 *= a0;
                    l1 *= a1;
#pragma unroll
                    for (int i = 0; i < 16; i++) {
                        o[4 * i] *= a0;
                        o[4 * i + 1] *= a0;
                        o[4 * i + 2] *= a1;
                        o[4 * i + 3] *= a1;
                    }
                    exp_pack(s, p, m0 * c, m1 * c, c, sum0, sum1);
                }
                l0 += sum0;
                l1 += sum1;
            }
        };
        using T_ = std::true_type;
        using F_ = std::false_type;

        for (int it = 0; it < my_tiles; it++) {
            const uint32_t qaddr = sbase + SM_Q + (it & 1) * TILE_BYTES + w * 8192;
            const int tile = cta + it * ncta;
            step(F_{}, T_{}, F_{}, qaddr, 0u, tile);
            if (it > 0)
                step(F_{}, F_{}, T_{}, qaddr, bars + 8 * (B_QE + ((it - 1) & 1)), tile);
            else
                step(F_{}, F_{}, F_{}, qaddr, 0u, tile);
            step(F_{}, F_{}, F_{}, qaddr, 0u, tile);
            if (it + 1 < my_tiles) {
                const int nq = (it + 1) & 1;
                mbar_wait(bars + 8 * (B_QF + nq), ((it + 1) >> 1) & 1);
                step(T_{}, F_{}, F_{}, sbase + SM_Q + nq * TILE_BYTES + w * 8192, qaddr, tile);
            } else {
                const uint32_t vs = st;
                mbar_wait(bars + 8 * (B_F + vs), ph);
                bar_sync(my_bar, 256);
                wgmma_fence();
                issue_pv<false>(o, p, sbase + SM_KV + vs * TILE_BYTES);
                wgmma_commit();
                bar_arrive(other_bar, 256);
                wgmma_wait<0>();
                fence_regs(o);
                release_kv(vs);
                epilogue(tile, qaddr);
            }
        }
        if ((tid & 127) == 0) asm volatile("cp.async.bulk.wait_group 0;" ::: "memory");
    }
}

typedef CUresult (*PFN_encodeTiled)(CUtensorMap*, CUtensorMapDataType, cuuint32_t, void*, const cuuint64_t*,
                                    const cuuint64_t*, const cuuint32_t*, const cuuint32_t*, CUtensorMapInterleave,
                                    CUtensorMapSwizzle, CUtensorMapL2promotion, CUtensorMapFloatOOBfill);

bool make_map(PFN_encodeTiled enc, CUtensorMap* tm, const void* ptr, int rows, int box_rows) {
    cuuint64_t dims[3] = {(cuuint64_t)HD, (cuuint64_t)rows, (cuuint64_t)NBH};
    cuuint64_t strides[2] = {(cuuint64_t)HD * 2, (cuuint64_t)rows * HD * 2};
    cuuint32_t box[3] = {64, (cuuint32_t)box_rows, 1};
    cuuint32_t estr[3] = {1, 1, 1};
    return enc(tm, CU_TENSOR_MAP_DATA_TYPE_BFLOAT16, 3, const_cast<void*>(ptr), dims, strides, box, estr,
               CU_TENSOR_MAP_INTERLEAVE_NONE, CU_TENSOR_MAP_SWIZZLE_128B, CU_TENSOR_MAP_L2_PROMOTION_L2_256B,
               CU_TENSOR_MAP_FLOAT_OOB_FILL_NONE) == CUDA_SUCCESS;
}

}

extern "C" void kernel_launch(void* const* d_in, const int* in_sizes, int n_in, void* d_out, int out_size) {
    static PFN_encodeTiled enc = nullptr;
    static int grid = 0;
    if (!enc) {
        void* fn = nullptr;
        cudaDriverEntryPointQueryResult qres;
        cudaGetDriverEntryPoint("cuTensorMapEncodeTiled", &fn, cudaEnableDefault, &qres);
        enc = (PFN_encodeTiled)fn;
        cudaFuncSetAttribute(gqa_attn_kernel, cudaFuncAttributeMaxDynamicSharedMemorySize, SMEM_BYTES);
        int dev = 0, sms = 0;
        cudaGetDevice(&dev);
        cudaDeviceGetAttribute(&sms, cudaDevAttrMultiProcessorCount, dev);
        grid = sms;
    }
    CUtensorMap tmQ, tmK, tmV, tmO;
    make_map(enc, &tmQ, d_in[0], QROWS, 128);
    make_map(enc, &tmK, d_in[1], SK, 128);
    make_map(enc, &tmV, d_in[2], SK, 128);
    make_map(enc, &tmO, d_out, QROWS, 64);
    gqa_attn_kernel<<<grid, NTHREADS, SMEM_BYTES>>>(tmQ, tmK, tmV, tmO);
}
```
